```python
import torch

def _softmax(x, axis=-1):
    return torch.softmax(x, dim=axis)
def _gelu(x):
    return torch.nn.functional.gelu(x, approximate="tanh")
def _silu(x):
    return torch.nn.functional.silu(x)
def _sigmoid(x):
    return torch.sigmoid(x)
def _layernorm(x, axis=-1, eps=1e-5):
    m = x.mean(dim=axis, keepdim=True)
    v = x.var(dim=axis, keepdim=True, unbiased=False)
    return (x - m) / torch.sqrt(v + eps)
def _scatter_add(tgt, idx, src, axis=0):
    return tgt.clone().index_add_(axis, idx, src)
def _segment_sum(src, seg, n):
    out = torch.zeros((n,) + src.shape[1:], dtype=src.dtype)
    return out.index_add_(0, seg, src)
def _pad(x, pw):
    flat = tuple(v for pair in reversed(pw) for v in pair)
    return torch.nn.functional.pad(x, flat)

kernel_name = 'standalone__fused_io_aware_attn__prompt'

def setup_inputs():

    _w = (lambda a: (lambda t: t.to(torch.bfloat16) if t.is_floating_point() else t)(torch.as_tensor(a)))
    B, H, S = 1, 32, 2048
    Dh = max(1, 512 // 32)
    return {
        "q": _w((lambda *s: torch.randn(*s, dtype=torch.bfloat16) * 0.8)(B, H, S, Dh)),
        "k": _w((lambda *s: torch.randn(*s, dtype=torch.bfloat16) * 0.8)(B, H, S, Dh)),
        "v": _w((lambda *s: torch.randn(*s, dtype=torch.bfloat16) * 0.05)(B, H, S, Dh)),
    }

def reference(q, k, v):
    scale = q.shape[-1] ** -0.5
    s = torch.einsum('bhqd,bhkd->bhqk', q, k) * scale
    p = _softmax(s, axis=-1)
    return torch.einsum('bhqk,bhkd->bhqd', p, v)
```

```cpp
#include <cuda_runtime.h>
#include <cuda_bf16.h>
#include <cuda.h>
#include <stdint.h>

#define NPOLY 32

static constexpr int SEQ = 2048;
static constexpr int NHEAD = 32;
static constexpr int QPC = 512;
static constexpr int NTHREADS = 512;
static constexpr int CHUNK = 128;
static constexpr int NCHUNK = SEQ / CHUNK;
static constexpr uint32_t OFF_K = 0;
static constexpr uint32_t OFF_V = 65536;
static constexpr uint32_t OFF_ONES = 131072;
static constexpr uint32_t OFF_BAR = OFF_ONES + 4096;
static constexpr uint32_t OFF_MISC = OFF_BAR + 8 * (NCHUNK + 1);
static constexpr uint32_t SMEM_BYTES = OFF_MISC + 64 + 1024;

template<int N, int SD> __device__ __forceinline__ void wg_qk(float* d, const uint32_t* a, uint64_t desc);
template<> __device__ __forceinline__ void wg_qk<16,0>(float* d, const uint32_t* a, uint64_t desc) {
  asm volatile("wgmma.mma_async.sync.aligned.m64n16k16.f32.bf16.bf16 {%0, %1, %2, %3, %4, %5, %6, %7}, {%8,%9,%10,%11}, %12, 0, 1, 1, 0;\n"
    : "+f"(d[0]), "+f"(d[1]), "+f"(d[2]), "+f"(d[3]), "+f"(d[4]), "+f"(d[5]), "+f"(d[6]), "+f"(d[7])
    : "r"(a[0]), "r"(a[1]), "r"(a[2]), "r"(a[3]), "l"(desc));
}
template<> __device__ __forceinline__ void wg_qk<16,1>(float* d, const uint32_t* a, uint64_t desc) {
  asm volatile("wgmma.mma_async.sync.aligned.m64n16k16.f32.bf16.bf16 {%0, %1, %2, %3, %4, %5, %6, %7}, {%8,%9,%10,%11}, %12, 1, 1, 1, 0;\n"
    : "+f"(d[0]), "+f"(d[1]), "+f"(d[2]), "+f"(d[3]), "+f"(d[4]), "+f"(d[5]), "+f"(d[6]), "+f"(d[7])
    : "r"(a[0]), "r"(a[1]), "r"(a[2]), "r"(a[3]), "l"(desc));
}
template<> __device__ __forceinline__ void wg_qk<32,0>(float* d, const uint32_t* a, uint64_t desc) {
  asm volatile("wgmma.mma_async.sync.aligned.m64n32k16.f32.bf16.bf16 {%0, %1, %2, %3, %4, %5, %6, %7, %8, %9, %10, %11, %12, %13, %14, %15}, {%16,%17,%18,%19}, %20, 0, 1, 1, 0;\n"
    : "+f"(d[0]), "+f"(d[1]), "+f"(d[2]), "+f"(d[3]), "+f"(d[4]), "+f"(d[5]), "+f"(d[6]), "+f"(d[7]), "+f"(d[8]), "+f"(d[9]), "+f"(d[10]), "+f"(d[11]), "+f"(d[12]), "+f"(d[13]), "+f"(d[14]), "+f"(d[15])
    : "r"(a[0]), "r"(a[1]), "r"(a[2]), "r"(a[3]), "l"(desc));
}
template<> __device__ __forceinline__ void wg_qk<32,1>(float* d, const uint32_t* a, uint64_t desc) {
  asm volatile("wgmma.mma_async.sync.aligned.m64n32k16.f32.bf16.bf16 {%0, %1, %2, %3, %4, %5, %6, %7, %8, %9, %10, %11, %12, %13, %14, %15}, {%16,%17,%18,%19}, %20, 1, 1, 1, 0;\n"
    : "+f"(d[0]), "+f"(d[1]), "+f"(d[2]), "+f"(d[3]), "+f"(d[4]), "+f"(d[5]), "+f"(d[6]), "+f"(d[7]), "+f"(d[8]), "+f"(d[9]), "+f"(d[10]), "+f"(d[11]), "+f"(d[12]), "+f"(d[13]), "+f"(d[14]), "+f"(d[15])
    : "r"(a[0]), "r"(a[1]), "r"(a[2]), "r"(a[3]), "l"(desc));
}
template<> __device__ __forceinline__ void wg_qk<48,0>(float* d, const uint32_t* a, uint64_t desc) {
  asm volatile("wgmma.mma_async.sync.aligned.m64n48k16.f32.bf16.bf16 {%0, %1, %2, %3, %4, %5, %6, %7, %8, %9, %10, %11, %12, %13, %14, %15, %16, %17, %18, %19, %20, %21, %22, %23}, {%24,%25,%26,%27}, %28, 0, 1, 1, 0;\n"
    : "+f"(d[0]), "+f"(d[1]), "+f"(d[2]), "+f"(d[3]), "+f"(d[4]), "+f"(d[5]), "+f"(d[6]), "+f"(d[7]), "+f"(d[8]), "+f"(d[9]), "+f"(d[10]), "+f"(d[11]), "+f"(d[12]), "+f"(d[13]), "+f"(d[14]), "+f"(d[15]), "+f"(d[16]), "+f"(d[17]), "+f"(d[18]), "+f"(d[19]), "+f"(d[20]), "+f"(d[21]), "+f"(d[22]), "+f"(d[23])
    : "r"(a[0]), "r"(a[1]), "r"(a[2]), "r"(a[3]), "l"(desc));
}
template<> __device__ __forceinline__ void wg_qk<48,1>(float* d, const uint32_t* a, uint64_t desc) {
  asm volatile("wgmma.mma_async.sync.aligned.m64n48k16.f32.bf16.bf16 {%0, %1, %2, %3, %4, %5, %6, %7, %8, %9, %10, %11, %12, %13, %14, %15, %16, %17, %18, %19, %20, %21, %22, %23}, {%24,%25,%26,%27}, %28, 1, 1, 1, 0;\n"
    : "+f"(d[0]), "+f"(d[1]), "+f"(d[2]), "+f"(d[3]), "+f"(d[4]), "+f"(d[5]), "+f"(d[6]), "+f"(d[7]), "+f"(d[8]), "+f"(d[9]), "+f"(d[10]), "+f"(d[11]), "+f"(d[12]), "+f"(d[13]), "+f"(d[14]), "+f"(d[15]), "+f"(d[16]), "+f"(d[17]), "+f"(d[18]), "+f"(d[19]), "+f"(d[20]), "+f"(d[21]), "+f"(d[22]), "+f"(d[23])
    : "r"(a[0]), "r"(a[1]), "r"(a[2]), "r"(a[3]), "l"(desc));
}
template<> __device__ __forceinline__ void wg_qk<64,0>(float* d, const uint32_t* a, uint64_t desc) {
  asm volatile("wgmma.mma_async.sync.aligned.m64n64k16.f32.bf16.bf16 {%0, %1, %2, %3, %4, %5, %6, %7, %8, %9, %10, %11, %12, %13, %14, %15, %16, %17, %18, %19, %20, %21, %22, %23, %24, %25, %26, %27, %28, %29, %30, %31}, {%32,%33,%34,%35}, %36, 0, 1, 1, 0;\n"
    : "+f"(d[0]), "+f"(d[1]), "+f"(d[2]), "+f"(d[3]), "+f"(d[4]), "+f"(d[5]), "+f"(d[6]), "+f"(d[7]), "+f"(d[8]), "+f"(d[9]), "+f"(d[10]), "+f"(d[11]), "+f"(d[12]), "+f"(d[13]), "+f"(d[14]), "+f"(d[15]), "+f"(d[16]), "+f"(d[17]), "+f"(d[18]), "+f"(d[19]), "+f"(d[20]), "+f"(d[21]), "+f"(d[22]), "+f"(d[23]), "+f"(d[24]), "+f"(d[25]), "+f"(d[26]), "+f"(d[27]), "+f"(d[28]), "+f"(d[29]), "+f"(d[30]), "+f"(d[31])
    : "r"(a[0]), "r"(a[1]), "r"(a[2]), "r"(a[3]), "l"(desc));
}
template<> __device__ __forceinline__ void wg_qk<64,1>(float* d, const uint32_t* a, uint64_t desc) {
  asm volatile("wgmma.mma_async.sync.aligned.m64n64k16.f32.bf16.bf16 {%0, %1, %2, %3, %4, %5, %6, %7, %8, %9, %10, %11, %12, %13, %14, %15, %16, %17, %18, %19, %20, %21, %22, %23, %24, %25, %26, %27, %28, %29, %30, %31}, {%32,%33,%34,%35}, %36, 1, 1, 1, 0;\n"
    : "+f"(d[0]), "+f"(d[1]), "+f"(d[2]), "+f"(d[3]), "+f"(d[4]), "+f"(d[5]), "+f"(d[6]), "+f"(d[7]), "+f"(d[8]), "+f"(d[9]), "+f"(d[10]), "+f"(d[11]), "+f"(d[12]), "+f"(d[13]), "+f"(d[14]), "+f"(d[15]), "+f"(d[16]), "+f"(d[17]), "+f"(d[18]), "+f"(d[19]), "+f"(d[20]), "+f"(d[21]), "+f"(d[22]), "+f"(d[23]), "+f"(d[24]), "+f"(d[25]), "+f"(d[26]), "+f"(d[27]), "+f"(d[28]), "+f"(d[29]), "+f"(d[30]), "+f"(d[31])
    : "r"(a[0]), "r"(a[1]), "r"(a[2]), "r"(a[3]), "l"(desc));
}
template<> __device__ __forceinline__ void wg_qk<80,0>(float* d, const uint32_t* a, uint64_t desc) {
  asm volatile("wgmma.mma_async.sync.aligned.m64n80k16.f32.bf16.bf16 {%0, %1, %2, %3, %4, %5, %6, %7, %8, %9, %10, %11, %12, %13, %14, %15, %16, %17, %18, %19, %20, %21, %22, %23, %24, %25, %26, %27, %28, %29, %30, %31, %32, %33, %34, %35, %36, %37, %38, %39}, {%40,%41,%42,%43}, %44, 0, 1, 1, 0;\n"
    : "+f"(d[0]), "+f"(d[1]), "+f"(d[2]), "+f"(d[3]), "+f"(d[4]), "+f"(d[5]), "+f"(d[6]), "+f"(d[7]), "+f"(d[8]), "+f"(d[9]), "+f"(d[10]), "+f"(d[11]), "+f"(d[12]), "+f"(d[13]), "+f"(d[14]), "+f"(d[15]), "+f"(d[16]), "+f"(d[17]), "+f"(d[18]), "+f"(d[19]), "+f"(d[20]), "+f"(d[21]), "+f"(d[22]), "+f"(d[23]), "+f"(d[24]), "+f"(d[25]), "+f"(d[26]), "+f"(d[27]), "+f"(d[28]), "+f"(d[29]), "+f"(d[30]), "+f"(d[31]), "+f"(d[32]), "+f"(d[33]), "+f"(d[34]), "+f"(d[35]), "+f"(d[36]), "+f"(d[37]), "+f"(d[38]), "+f"(d[39])
    : "r"(a[0]), "r"(a[1]), "r"(a[2]), "r"(a[3]), "l"(desc));
}
template<> __device__ __forceinline__ void wg_qk<80,1>(float* d, const uint32_t* a, uint64_t desc) {
  asm volatile("wgmma.mma_async.sync.aligned.m64n80k16.f32.bf16.bf16 {%0, %1, %2, %3, %4, %5, %6, %7, %8, %9, %10, %11, %12, %13, %14, %15, %16, %17, %18, %19, %20, %21, %22, %23, %24, %25, %26, %27, %28, %29, %30, %31, %32, %33, %34, %35, %36, %37, %38, %39}, {%40,%41,%42,%43}, %44, 1, 1, 1, 0;\n"
    : "+f"(d[0]), "+f"(d[1]), "+f"(d[2]), "+f"(d[3]), "+f"(d[4]), "+f"(d[5]), "+f"(d[6]), "+f"(d[7]), "+f"(d[8]), "+f"(d[9]), "+f"(d[10]), "+f"(d[11]), "+f"(d[12]), "+f"(d[13]), "+f"(d[14]), "+f"(d[15]), "+f"(d[16]), "+f"(d[17]), "+f"(d[18]), "+f"(d[19]), "+f"(d[20]), "+f"(d[21]), "+f"(d[22]), "+f"(d[23]), "+f"(d[24]), "+f"(d[25]), "+f"(d[26]), "+f"(d[27]), "+f"(d[28]), "+f"(d[29]), "+f"(d[30]), "+f"(d[31]), "+f"(d[32]), "+f"(d[33]), "+f"(d[34]), "+f"(d[35]), "+f"(d[36]), "+f"(d[37]), "+f"(d[38]), "+f"(d[39])
    : "r"(a[0]), "r"(a[1]), "r"(a[2]), "r"(a[3]), "l"(desc));
}
template<> __device__ __forceinline__ void wg_qk<96,0>(float* d, const uint32_t* a, uint64_t desc) {
  asm volatile("wgmma.mma_async.sync.aligned.m64n96k16.f32.bf16.bf16 {%0, %1, %2, %3, %4, %5, %6, %7, %8, %9, %10, %11, %12, %13, %14, %15, %16, %17, %18, %19, %20, %21, %22, %23, %24, %25, %26, %27, %28, %29, %30, %31, %32, %33, %34, %35, %36, %37, %38, %39, %40, %41, %42, %43, %44, %45, %46, %47}, {%48,%49,%50,%51}, %52, 0, 1, 1, 0;\n"
    : "+f"(d[0]), "+f"(d[1]), "+f"(d[2]), "+f"(d[3]), "+f"(d[4]), "+f"(d[5]), "+f"(d[6]), "+f"(d[7]), "+f"(d[8]), "+f"(d[9]), "+f"(d[10]), "+f"(d[11]), "+f"(d[12]), "+f"(d[13]), "+f"(d[14]), "+f"(d[15]), "+f"(d[16]), "+f"(d[17]), "+f"(d[18]), "+f"(d[19]), "+f"(d[20]), "+f"(d[21]), "+f"(d[22]), "+f"(d[23]), "+f"(d[24]), "+f"(d[25]), "+f"(d[26]), "+f"(d[27]), "+f"(d[28]), "+f"(d[29]), "+f"(d[30]), "+f"(d[31]), "+f"(d[32]), "+f"(d[33]), "+f"(d[34]), "+f"(d[35]), "+f"(d[36]), "+f"(d[37]), "+f"(d[38]), "+f"(d[39]), "+f"(d[40]), "+f"(d[41]), "+f"(d[42]), "+f"(d[43]), "+f"(d[44]), "+f"(d[45]), "+f"(d[46]), "+f"(d[47])
    : "r"(a[0]), "r"(a[1]), "r"(a[2]), "r"(a[3]), "l"(desc));
}
template<> __device__ __forceinline__ void wg_qk<96,1>(float* d, const uint32_t* a, uint64_t desc) {
  asm volatile("wgmma.mma_async.sync.aligned.m64n96k16.f32.bf16.bf16 {%0, %1, %2, %3, %4, %5, %6, %7, %8, %9, %10, %11, %12, %13, %14, %15, %16, %17, %18, %19, %20, %21, %22, %23, %24, %25, %26, %27, %28, %29, %30, %31, %32, %33, %34, %35, %36, %37, %38, %39, %40, %41, %42, %43, %44, %45, %46, %47}, {%48,%49,%50,%51}, %52, 1, 1, 1, 0;\n"
    : "+f"(d[0]), "+f"(d[1]), "+f"(d[2]), "+f"(d[3]), "+f"(d[4]), "+f"(d[5]), "+f"(d[6]), "+f"(d[7]), "+f"(d[8]), "+f"(d[9]), "+f"(d[10]), "+f"(d[11]), "+f"(d[12]), "+f"(d[13]), "+f"(d[14]), "+f"(d[15]), "+f"(d[16]), "+f"(d[17]), "+f"(d[18]), "+f"(d[19]), "+f"(d[20]), "+f"(d[21]), "+f"(d[22]), "+f"(d[23]), "+f"(d[24]), "+f"(d[25]), "+f"(d[26]), "+f"(d[27]), "+f"(d[28]), "+f"(d[29]), "+f"(d[30]), "+f"(d[31]), "+f"(d[32]), "+f"(d[33]), "+f"(d[34]), "+f"(d[35]), "+f"(d[36]), "+f"(d[37]), "+f"(d[38]), "+f"(d[39]), "+f"(d[40]), "+f"(d[41]), "+f"(d[42]), "+f"(d[43]), "+f"(d[44]), "+f"(d[45]), "+f"(d[46]), "+f"(d[47])
    : "r"(a[0]), "r"(a[1]), "r"(a[2]), "r"(a[3]), "l"(desc));
}
template<> __device__ __forceinline__ void wg_qk<112,0>(float* d, const uint32_t* a, uint64_t desc) {
  asm volatile("wgmma.mma_async.sync.aligned.m64n112k16.f32.bf16.bf16 {%0, %1, %2, %3, %4, %5, %6, %7, %8, %9, %10, %11, %12, %13, %14, %15, %16, %17, %18, %19, %20, %21, %22, %23, %24, %25, %26, %27, %28, %29, %30, %31, %32, %33, %34, %35, %36, %37, %38, %39, %40, %41, %42, %43, %44, %45, %46, %47, %48, %49, %50, %51, %52, %53, %54, %55}, {%56,%57,%58,%59}, %60, 0, 1, 1, 0;\n"
    : "+f"(d[0]), "+f"(d[1]), "+f"(d[2]), "+f"(d[3]), "+f"(d[4]), "+f"(d[5]), "+f"(d[6]), "+f"(d[7]), "+f"(d[8]), "+f"(d[9]), "+f"(d[10]), "+f"(d[11]), "+f"(d[12]), "+f"(d[13]), "+f"(d[14]), "+f"(d[15]), "+f"(d[16]), "+f"(d[17]), "+f"(d[18]), "+f"(d[19]), "+f"(d[20]), "+f"(d[21]), "+f"(d[22]), "+f"(d[23]), "+f"(d[24]), "+f"(d[25]), "+f"(d[26]), "+f"(d[27]), "+f"(d[28]), "+f"(d[29]), "+f"(d[30]), "+f"(d[31]), "+f"(d[32]), "+f"(d[33]), "+f"(d[34]), "+f"(d[35]), "+f"(d[36]), "+f"(d[37]), "+f"(d[38]), "+f"(d[39]), "+f"(d[40]), "+f"(d[41]), "+f"(d[42]), "+f"(d[43]), "+f"(d[44]), "+f"(d[45]), "+f"(d[46]), "+f"(d[47]), "+f"(d[48]), "+f"(d[49]), "+f"(d[50]), "+f"(d[51]), "+f"(d[52]), "+f"(d[53]), "+f"(d[54]), "+f"(d[55])
    : "r"(a[0]), "r"(a[1]), "r"(a[2]), "r"(a[3]), "l"(desc));
}
template<> __device__ __forceinline__ void wg_qk<112,1>(float* d, const uint32_t* a, uint64_t desc) {
  asm volatile("wgmma.mma_async.sync.aligned.m64n112k16.f32.bf16.bf16 {%0, %1, %2, %3, %4, %5, %6, %7, %8, %9, %10, %11, %12, %13, %14, %15, %16, %17, %18, %19, %20, %21, %22, %23, %24, %25, %26, %27, %28, %29, %30, %31, %32, %33, %34, %35, %36, %37, %38, %39, %40, %41, %42, %43, %44, %45, %46, %47, %48, %49, %50, %51, %52, %53, %54, %55}, {%56,%57,%58,%59}, %60, 1, 1, 1, 0;\n"
    : "+f"(d[0]), "+f"(d[1]), "+f"(d[2]), "+f"(d[3]), "+f"(d[4]), "+f"(d[5]), "+f"(d[6]), "+f"(d[7]), "+f"(d[8]), "+f"(d[9]), "+f"(d[10]), "+f"(d[11]), "+f"(d[12]), "+f"(d[13]), "+f"(d[14]), "+f"(d[15]), "+f"(d[16]), "+f"(d[17]), "+f"(d[18]), "+f"(d[19]), "+f"(d[20]), "+f"(d[21]), "+f"(d[22]), "+f"(d[23]), "+f"(d[24]), "+f"(d[25]), "+f"(d[26]), "+f"(d[27]), "+f"(d[28]), "+f"(d[29]), "+f"(d[30]), "+f"(d[31]), "+f"(d[32]), "+f"(d[33]), "+f"(d[34]), "+f"(d[35]), "+f"(d[36]), "+f"(d[37]), "+f"(d[38]), "+f"(d[39]), "+f"(d[40]), "+f"(d[41]), "+f"(d[42]), "+f"(d[43]), "+f"(d[44]), "+f"(d[45]), "+f"(d[46]), "+f"(d[47]), "+f"(d[48]), "+f"(d[49]), "+f"(d[50]), "+f"(d[51]), "+f"(d[52]), "+f"(d[53]), "+f"(d[54]), "+f"(d[55])
    : "r"(a[0]), "r"(a[1]), "r"(a[2]), "r"(a[3]), "l"(desc));
}
template<> __device__ __forceinline__ void wg_qk<128,0>(float* d, const uint32_t* a, uint64_t desc) {
  asm volatile("wgmma.mma_async.sync.aligned.m64n128k16.f32.bf16.bf16 {%0, %1, %2, %3, %4, %5, %6, %7, %8, %9, %10, %11, %12, %13, %14, %15, %16, %17, %18, %19, %20, %21, %22, %23, %24, %25, %26, %27, %28, %29, %30, %31, %32, %33, %34, %35, %36, %37, %38, %39, %40, %41, %42, %43, %44, %45, %46, %47, %48, %49, %50, %51, %52, %53, %54, %55, %56, %57, %58, %59, %60, %61, %62, %63}, {%64,%65,%66,%67}, %68, 0, 1, 1, 0;\n"
    : "+f"(d[0]), "+f"(d[1]), "+f"(d[2]), "+f"(d[3]), "+f"(d[4]), "+f"(d[5]), "+f"(d[6]), "+f"(d[7]), "+f"(d[8]), "+f"(d[9]), "+f"(d[10]), "+f"(d[11]), "+f"(d[12]), "+f"(d[13]), "+f"(d[14]), "+f"(d[15]), "+f"(d[16]), "+f"(d[17]), "+f"(d[18]), "+f"(d[19]), "+f"(d[20]), "+f"(d[21]), "+f"(d[22]), "+f"(d[23]), "+f"(d[24]), "+f"(d[25]), "+f"(d[26]), "+f"(d[27]), "+f"(d[28]), "+f"(d[29]), "+f"(d[30]), "+f"(d[31]), "+f"(d[32]), "+f"(d[33]), "+f"(d[34]), "+f"(d[35]), "+f"(d[36]), "+f"(d[37]), "+f"(d[38]), "+f"(d[39]), "+f"(d[40]), "+f"(d[41]), "+f"(d[42]), "+f"(d[43]), "+f"(d[44]), "+f"(d[45]), "+f"(d[46]), "+f"(d[47]), "+f"(d[48]), "+f"(d[49]), "+f"(d[50]), "+f"(d[51]), "+f"(d[52]), "+f"(d[53]), "+f"(d[54]), "+f"(d[55]), "+f"(d[56]), "+f"(d[57]), "+f"(d[58]), "+f"(d[59]), "+f"(d[60]), "+f"(d[61]), "+f"(d[62]), "+f"(d[63])
    : "r"(a[0]), "r"(a[1]), "r"(a[2]), "r"(a[3]), "l"(desc));
}
template<> __device__ __forceinline__ void wg_qk<128,1>(float* d, const uint32_t* a, uint64_t desc) {
  asm volatile("wgmma.mma_async.sync.aligned.m64n128k16.f32.bf16.bf16 {%0, %1, %2, %3, %4, %5, %6, %7, %8, %9, %10, %11, %12, %13, %14, %15, %16, %17, %18, %19, %20, %21, %22, %23, %24, %25, %26, %27, %28, %29, %30, %31, %32, %33, %34, %35, %36, %37, %38, %39, %40, %41, %42, %43, %44, %45, %46, %47, %48, %49, %50, %51, %52, %53, %54, %55, %56, %57, %58, %59, %60, %61, %62, %63}, {%64,%65,%66,%67}, %68, 1, 1, 1, 0;\n"
    : "+f"(d[0]), "+f"(d[1]), "+f"(d[2]), "+f"(d[3]), "+f"(d[4]), "+f"(d[5]), "+f"(d[6]), "+f"(d[7]), "+f"(d[8]), "+f"(d[9]), "+f"(d[10]), "+f"(d[11]), "+f"(d[12]), "+f"(d[13]), "+f"(d[14]), "+f"(d[15]), "+f"(d[16]), "+f"(d[17]), "+f"(d[18]), "+f"(d[19]), "+f"(d[20]), "+f"(d[21]), "+f"(d[22]), "+f"(d[23]), "+f"(d[24]), "+f"(d[25]), "+f"(d[26]), "+f"(d[27]), "+f"(d[28]), "+f"(d[29]), "+f"(d[30]), "+f"(d[31]), "+f"(d[32]), "+f"(d[33]), "+f"(d[34]), "+f"(d[35]), "+f"(d[36]), "+f"(d[37]), "+f"(d[38]), "+f"(d[39]), "+f"(d[40]), "+f"(d[41]), "+f"(d[42]), "+f"(d[43]), "+f"(d[44]), "+f"(d[45]), "+f"(d[46]), "+f"(d[47]), "+f"(d[48]), "+f"(d[49]), "+f"(d[50]), "+f"(d[51]), "+f"(d[52]), "+f"(d[53]), "+f"(d[54]), "+f"(d[55]), "+f"(d[56]), "+f"(d[57]), "+f"(d[58]), "+f"(d[59]), "+f"(d[60]), "+f"(d[61]), "+f"(d[62]), "+f"(d[63])
    : "r"(a[0]), "r"(a[1]), "r"(a[2]), "r"(a[3]), "l"(desc));
}
template<int SA> __device__ __forceinline__ void wg_pv(float* d, const uint32_t* a, uint64_t desc);
template<> __device__ __forceinline__ void wg_pv<1>(float* d, const uint32_t* a, uint64_t desc) {
  asm volatile("wgmma.mma_async.sync.aligned.m64n24k16.f32.bf16.bf16 {%0, %1, %2, %3, %4, %5, %6, %7, %8, %9, %10, %11}, {%12,%13,%14,%15}, %16, 1, 1, 1, 1;\n"
    : "+f"(d[0]), "+f"(d[1]), "+f"(d[2]), "+f"(d[3]), "+f"(d[4]), "+f"(d[5]), "+f"(d[6]), "+f"(d[7]), "+f"(d[8]), "+f"(d[9]), "+f"(d[10]), "+f"(d[11])
    : "r"(a[0]), "r"(a[1]), "r"(a[2]), "r"(a[3]), "l"(desc));
}
template<> __device__ __forceinline__ void wg_pv<-1>(float* d, const uint32_t* a, uint64_t desc) {
  asm volatile("wgmma.mma_async.sync.aligned.m64n24k16.f32.bf16.bf16 {%0, %1, %2, %3, %4, %5, %6, %7, %8, %9, %10, %11}, {%12,%13,%14,%15}, %16, 1, -1, 1, 1;\n"
    : "+f"(d[0]), "+f"(d[1]), "+f"(d[2]), "+f"(d[3]), "+f"(d[4]), "+f"(d[5]), "+f"(d[6]), "+f"(d[7]), "+f"(d[8]), "+f"(d[9]), "+f"(d[10]), "+f"(d[11])
    : "r"(a[0]), "r"(a[1]), "r"(a[2]), "r"(a[3]), "l"(desc));
}

__device__ __forceinline__ void wg_fence() { asm volatile("wgmma.fence.sync.aligned;" ::: "memory"); }
__device__ __forceinline__ void wg_commit() { asm volatile("wgmma.commit_group.sync.aligned;" ::: "memory"); }
template<int N> __device__ __forceinline__ void wg_wait() { asm volatile("wgmma.wait_group.sync.aligned %0;" :: "n"(N) : "memory"); }

__device__ __forceinline__ void mbar_init(uint32_t bar, uint32_t count) {
    asm volatile("mbarrier.init.shared::cta.b64 [%0], %1;" :: "r"(bar), "r"(count) : "memory");
}
__device__ __forceinline__ void mbar_expect_tx(uint32_t bar, uint32_t bytes) {
    asm volatile("mbarrier.arrive.expect_tx.shared::cta.b64 _, [%0], %1;" :: "r"(bar), "r"(bytes) : "memory");
}
__device__ __forceinline__ void mbar_arrive(uint32_t bar) {
    asm volatile("mbarrier.arrive.shared::cta.b64 _, [%0];" :: "r"(bar) : "memory");
}
__device__ __forceinline__ void mbar_wait(uint32_t bar, uint32_t parity) {
    uint32_t done;
    uint32_t tries = 0;
    do {
        asm volatile("{\n.reg .pred p;\nmbarrier.try_wait.parity.shared::cta.b64 p, [%1], %2;\nselp.u32 %0, 1, 0, p;\n}\n"
                     : "=r"(done) : "r"(bar), "r"(parity) : "memory");
        if (!done && ++tries > (1u << 22)) __trap();
    } while (!done);
}
__device__ __forceinline__ void tma_load_2d(uint32_t dst, const CUtensorMap* map, int c0, int c1, uint32_t bar) {
    asm volatile("cp.async.bulk.tensor.2d.shared::cluster.global.mbarrier::complete_tx::bytes [%0], [%1, {%3, %4}], [%2];"
                 :: "r"(dst), "l"(map), "r"(bar), "r"(c0), "r"(c1) : "memory");
}
__device__ __forceinline__ float ex2(float x) { float y; asm("ex2.approx.ftz.f32 %0, %1;" : "=f"(y) : "f"(x)); return y; }
__device__ __forceinline__ uint32_t pack_bf16(float lo, float hi) {
    uint32_t r; asm("cvt.rn.bf16x2.f32 %0, %1, %2;" : "=r"(r) : "f"(hi), "f"(lo)); return r;
}
__device__ __forceinline__ uint32_t exp2_pair(float tlo, float thi) {
    uint32_t y = __byte_perm(__float_as_uint(tlo), __float_as_uint(thi), 0x6521);
    uint32_t gh = (y & 0x007F007Fu) | 0x3F003F00u;
    uint32_t e = y & 0xFF80FF80u;
    uint32_t r; asm("fma.rn.bf16x2 %0, %1, %2, %3;" : "=r"(r) : "r"(gh), "r"(y), "r"(e));
    return r;
}
__device__ __forceinline__ uint64_t mk_desc(uint32_t lo, uint32_t hi) { return ((uint64_t)hi << 32) | lo; }

static constexpr float QSCALE = 0.25f * 1.4426950408889634f;
static constexpr uint32_t DESC_HI = (256u >> 4) | (3u << 30);
static constexpr uint32_t VSTEP = 32u - (32u << 16);

template<int NP>
__device__ __forceinline__ void issue_qk(float* s, const uint32_t* qa, const uint32_t* ma, uint32_t kd, uint32_t od) {
    if (NP > 0) {
        wg_qk<(NP > 0 ? NP : 16), 0>(s, qa, mk_desc(kd, DESC_HI));
        wg_qk<(NP > 0 ? NP : 16), 1>(s, ma, mk_desc(od, DESC_HI));
    }
    if (NP < 64) wg_qk<(NP < 64 ? 64 - NP : 16), 0>(s + NP / 2, qa, mk_desc(kd + NP * 2, DESC_HI));
}
template<int NP>
__device__ __forceinline__ void softmax_tile(const float* s, uint32_t* p) {
    #pragma unroll
    for (int i = 0; i < 16; i++) {
        if (i < NP / 4) p[i] = exp2_pair(s[2 * i], s[2 * i + 1]);
        else p[i] = pack_bf16(ex2(s[2 * i]), ex2(s[2 * i + 1]));
    }
}
template<int NP>
__device__ __forceinline__ void issue_pv(float* o, const uint32_t* p, uint32_t vd) {
    #pragma unroll
    for (int k = 0; k < 4; k++) {
        if (k < NP / 16) wg_pv<-1>(o, p + 4 * k, mk_desc(vd + k * VSTEP, DESC_HI));
        else wg_pv<1>(o, p + 4 * k, mk_desc(vd + k * VSTEP, DESC_HI));
    }
}

__device__ __forceinline__ void store_out(__nv_bfloat16* out, int row0, int lane, const float* o) {
    const int g = lane >> 2, t = lane & 3;
    const float r0 = 1.0f / o[8], r1 = 1.0f / o[10];
    uint32_t* p0 = reinterpret_cast<uint32_t*>(out + (size_t)(row0 + g) * 16) + t;
    uint32_t* p1 = reinterpret_cast<uint32_t*>(out + (size_t)(row0 + g + 8) * 16) + t;
    p0[0] = pack_bf16(o[0] * r0, o[1] * r0);
    p0[4] = pack_bf16(o[4] * r0, o[5] * r0);
    p1[0] = pack_bf16(o[2] * r1, o[3] * r1);
    p1[4] = pack_bf16(o[6] * r1, o[7] * r1);
}

__device__ __forceinline__ void safe_block(const __nv_bfloat16* __restrict__ q, __nv_bfloat16* __restrict__ out,
                                        int row0, int lane, uint32_t kd0, uint32_t vd0) {
    const int g = lane >> 2, t = lane & 3;
    const uint32_t* q0 = reinterpret_cast<const uint32_t*>(q + (size_t)(row0 + g) * 16) + t;
    const uint32_t* q1 = reinterpret_cast<const uint32_t*>(q + (size_t)(row0 + g + 8) * 16) + t;
    uint32_t qa[4] = {q0[0], q1[0], q0[4], q1[4]};
    float o[12];
    #pragma unroll
    for (int i = 0; i < 12; i++) o[i] = 0.f;
    float m0 = -INFINITY, m1 = -INFINITY;
    #pragma unroll 1
    for (int j = 0; j < SEQ / 64; j++) {
        float s[32];
        uint32_t p[16];
        wg_fence();
        wg_qk<64, 0>(s, qa, mk_desc(kd0 + j * 128, DESC_HI));
        wg_commit();
        wg_wait<0>();
        float x0 = m0, x1 = m1;
        #pragma unroll
        for (int i = 0; i < 8; i++) {
            x0 = fmaxf(x0, fmaxf(s[4 * i], s[4 * i + 1]));
            x1 = fmaxf(x1, fmaxf(s[4 * i + 2], s[4 * i + 3]));
        }
        x0 = fmaxf(x0, __shfl_xor_sync(0xffffffffu, x0, 1));
        x0 = fmaxf(x0, __shfl_xor_sync(0xffffffffu, x0, 2));
        x1 = fmaxf(x1, __shfl_xor_sync(0xffffffffu, x1, 1));
        x1 = fmaxf(x1, __shfl_xor_sync(0xffffffffu, x1, 2));
        const float a0 = exp2f((m0 - x0) * QSCALE), a1 = exp2f((m1 - x1) * QSCALE);
        m0 = x0; m1 = x1;
        #pragma unroll
        for (int i = 0; i < 3; i++) { o[4 * i] *= a0; o[4 * i + 1] *= a0; o[4 * i + 2] *= a1; o[4 * i + 3] *= a1; }
        #pragma unroll
        for (int i = 0; i < 8; i++) {
            p[2 * i] = pack_bf16(exp2f((s[4 * i] - m0) * QSCALE), exp2f((s[4 * i + 1] - m0) * QSCALE));
            p[2 * i + 1] = pack_bf16(exp2f((s[4 * i + 2] - m1) * QSCALE), exp2f((s[4 * i + 3] - m1) * QSCALE));
        }
        wg_fence();
        issue_pv<0>(o, p, vd0 + j * 4 * VSTEP);
        wg_commit();
        wg_wait<0>();
    }
    store_out(out, row0, lane, o);
}

__global__ void __launch_bounds__(NTHREADS, 1)
attn_kernel(const __grid_constant__ CUtensorMap tmK, const __grid_constant__ CUtensorMap tmV,
            const __nv_bfloat16* __restrict__ q, __nv_bfloat16* __restrict__ out) {
    extern __shared__ uint8_t smem_raw[];
    const uint32_t sbase = ((uint32_t)__cvta_generic_to_shared(smem_raw) + 1023u) & ~1023u;
    uint8_t* sptr = smem_raw + (sbase - (uint32_t)__cvta_generic_to_shared(smem_raw));
    const int tid = threadIdx.x, lane = tid & 31, warp = tid >> 5, wg = tid >> 7;
    const int head = blockIdx.x >> 2, quarter = blockIdx.x & 3;
    const uint32_t bar0 = sbase + OFF_BAR;
    const uint32_t barN = bar0 + 8 * NCHUNK;
    uint32_t* kmax_s = reinterpret_cast<uint32_t*>(sptr + OFF_MISC);

    if (tid == 0) {
        #pragma unroll 1
        for (int c = 0; c < NCHUNK; c++) mbar_init(bar0 + 8 * c, 1);
        mbar_init(barN, NTHREADS / 32);
        *kmax_s = 0u;
        asm volatile("fence.mbarrier_init.release.cluster;" ::: "memory");
        asm volatile("fence.proxy.async.shared::cta;" ::: "memory");
        #pragma unroll 1
        for (int c = 0; c < NCHUNK; c++) {
            mbar_expect_tx(bar0 + 8 * c, 2 * CHUNK * 32);
            tma_load_2d(sbase + OFF_K + c * CHUNK * 32, &tmK, 0, head * SEQ + c * CHUNK, bar0 + 8 * c);
            tma_load_2d(sbase + OFF_V + c * CHUNK * 32, &tmV, 0, head * SEQ + c * CHUNK, bar0 + 8 * c);
        }
    }
    reinterpret_cast<uint2*>(sptr + OFF_ONES)[tid] = make_uint2(0x3F803F80u, 0x3F803F80u);
    asm volatile("fence.proxy.async.shared::cta;" ::: "memory");
    __syncthreads();

    const int g = lane >> 2, t = lane & 3;
    uint32_t ma[4];
    ma[0] = ma[1] = (t == 0) ? 0x3ED643BFu   : ((t == 1) ? 0x0000B9A8u   : 0u);
    ma[2] = ma[3] = 0u;
    const uint32_t kd0 = ((sbase + OFF_K) >> 4) | (1u << 16);
    const uint32_t vd0 = ((sbase + OFF_V) >> 4) | (((OFF_ONES - OFF_V) >> 4) << 16);
    const uint32_t od = ((sbase + OFF_ONES) >> 4) | (1u << 16);

    bool bad = false;
    float qn2 = 0.f;
    #pragma unroll 1
    for (int pass = 0; pass < 2; pass++) {
        const int row0 = head * SEQ + quarter * QPC + (pass * 4 + wg) * 64 + (warp & 3) * 16;
        uint32_t qa[4];
        {
            const uint32_t* q0 = reinterpret_cast<const uint32_t*>(q + (size_t)(row0 + g) * 16) + t;
            const uint32_t* q1 = reinterpret_cast<const uint32_t*>(q + (size_t)(row0 + g + 8) * 16) + t;
            uint32_t raw[4] = {q0[0], q1[0], q0[4], q1[4]};
            float n[2] = {0.f, 0.f};
            #pragma unroll
            for (int i = 0; i < 4; i++) {
                qa[i] = pack_bf16(__uint_as_float(raw[i] << 16) * QSCALE, __uint_as_float(raw[i] & 0xffff0000u) * QSCALE);
                const float lo = __uint_as_float(qa[i] << 16), hi = __uint_as_float(qa[i] & 0xffff0000u);
                n[i & 1] += lo * lo + hi * hi;
            }
            #pragma unroll
            for (int i = 0; i < 2; i++) {
                n[i] += __shfl_xor_sync(0xffffffffu, n[i], 1);
                n[i] += __shfl_xor_sync(0xffffffffu, n[i], 2);
                if (!(n[i] <= qn2)) qn2 = n[i];
            }
        }
        float o[12];
        #pragma unroll
        for (int i = 0; i < 12; i++) o[i] = 0.f;
        float s0[32], s1[32];
        uint32_t p0[16], p1[16];

        mbar_wait(bar0, 0);
        wg_fence();
        issue_qk<NPOLY>(s0, qa, ma, kd0, od);
        wg_commit();
        wg_commit();
        #pragma unroll 1
        for (int c = 0; c < NCHUNK; c++) {
            const uint32_t kd = kd0 + c * (CHUNK * 2);
            const uint32_t vd = vd0 + c * (8 * VSTEP);
            wg_wait<1>();
            wg_fence();
            issue_qk<NPOLY>(s1, qa, ma, kd + 128, od);
            wg_commit();
            softmax_tile<NPOLY>(s0, p0);
            wg_fence();
            issue_pv<NPOLY>(o, p0, vd);
            wg_commit();
            if (c + 1 < NCHUNK) mbar_wait(bar0 + 8 * (c + 1), 0);
            wg_wait<1>();
            wg_fence();
            issue_qk<NPOLY>(s0, qa, ma, (c + 1 < NCHUNK) ? kd + 256 : kd0, od);
            wg_commit();
            softmax_tile<NPOLY>(s1, p1);
            wg_fence();
            issue_pv<NPOLY>(o, p1, vd + 4 * VSTEP);
            wg_commit();
        }
        wg_wait<0>();
        {
            float amax0 = fmaxf(fmaxf(fabsf(o[0]), fabsf(o[1])), fmaxf(fabsf(o[4]), fabsf(o[5])));
            float amax1 = fmaxf(fmaxf(fabsf(o[2]), fabsf(o[3])), fmaxf(fabsf(o[6]), fabsf(o[7])));
            float sum = o[0] + o[1] + o[2] + o[3] + o[4] + o[5] + o[6] + o[7];
            if (!(fabsf(sum) < 1e37f) || !(amax0 > 1e-25f) || !(amax1 > 1e-25f)) bad = true;
        }
        store_out(out, row0, lane, o);
        if (pass == 0) {
            uint32_t m2 = 0u;
            const uint4* kp = reinterpret_cast<const uint4*>(sptr + OFF_K + warp * 4096) + lane;
            #pragma unroll
            for (int i = 0; i < 8; i++) {
                const uint4 w = kp[32 * i];
                uint32_t a;
                asm("mul.rn.bf16x2 %0, %1, %1;" : "=r"(a) : "r"(w.x));
                asm("fma.rn.bf16x2 %0, %1, %1, %0;" : "+r"(a) : "r"(w.y));
                asm("fma.rn.bf16x2 %0, %1, %1, %0;" : "+r"(a) : "r"(w.z));
                asm("fma.rn.bf16x2 %0, %1, %1, %0;" : "+r"(a) : "r"(w.w));
                float sN = __uint_as_float(a << 16) + __uint_as_float(a & 0xffff0000u);
                sN += __shfl_xor_sync(0xffffffffu, sN, 1);
                m2 = max(m2, __float_as_uint(sN) & 0x7fffffffu);
            }
            m2 = __reduce_max_sync(0xffffffffu, m2);
            if (lane == 0) { atomicMax(kmax_s, m2); mbar_arrive(barN); }
        }
    }
    mbar_wait(barN, 0);
    const float kn2 = __uint_as_float(*reinterpret_cast<volatile uint32_t*>(kmax_s));
    if (!(qn2 * kn2 * 1.1f <= 32.f * 32.f)) bad = true;
    uint32_t anybad;
    asm volatile("{\n.reg .pred p, q;\nsetp.ne.u32 q, %1, 0;\nbarrier.cta.red.or.aligned.pred p, %2, 128, q;\nselp.u32 %0, 1, 0, p;\n}\n"
                 : "=r"(anybad) : "r"((uint32_t)bad), "r"(wg + 1) : "memory");
    if (anybad) {
        #pragma unroll 1
        for (int pass = 0; pass < 2; pass++) {
            const int row0 = head * SEQ + quarter * QPC + (pass * 4 + wg) * 64 + (warp & 3) * 16;
            safe_block(q, out, row0, lane, kd0, vd0);
        }
    }
}

typedef CUresult (*PFN_encodeTiled)(CUtensorMap*, CUtensorMapDataType, cuuint32_t, void*, const cuuint64_t*, const cuuint64_t*,
                                    const cuuint32_t*, const cuuint32_t*, CUtensorMapInterleave, CUtensorMapSwizzle,
                                    CUtensorMapL2promotion, CUtensorMapFloatOOBfill);

extern "C" void kernel_launch(void* const* d_in, const int* in_sizes, int n_in, void* d_out, int out_size) {
    static PFN_encodeTiled encode = nullptr;
    if (!encode) {
        cudaDriverEntryPointQueryResult qres;
        void* fn = nullptr;
        cudaGetDriverEntryPoint("cuTensorMapEncodeTiled", &fn, cudaEnableDefault, &qres);
        encode = (PFN_encodeTiled)fn;
        cudaFuncSetAttribute(attn_kernel, cudaFuncAttributeMaxDynamicSharedMemorySize, SMEM_BYTES);
    }
    CUtensorMap tmK, tmV;
    cuuint64_t gdim[2] = {16, (cuuint64_t)NHEAD * SEQ};
    cuuint64_t gstr[1] = {32};
    cuuint32_t box[2] = {16, (cuuint32_t)CHUNK};
    cuuint32_t estr[2] = {1, 1};
    encode(&tmK, CU_TENSOR_MAP_DATA_TYPE_BFLOAT16, 2, d_in[1], gdim, gstr, box, estr, CU_TENSOR_MAP_INTERLEAVE_NONE,
           CU_TENSOR_MAP_SWIZZLE_32B, CU_TENSOR_MAP_L2_PROMOTION_L2_256B, CU_TENSOR_MAP_FLOAT_OOB_FILL_NONE);
    encode(&tmV, CU_TENSOR_MAP_DATA_TYPE_BFLOAT16, 2, d_in[2], gdim, gstr, box, estr, CU_TENSOR_MAP_INTERLEAVE_NONE,
           CU_TENSOR_MAP_SWIZZLE_32B, CU_TENSOR_MAP_L2_PROMOTION_L2_256B, CU_TENSOR_MAP_FLOAT_OOB_FILL_NONE);
    attn_kernel<<<NHEAD * (SEQ / QPC), NTHREADS, SMEM_BYTES>>>(tmK, tmV, (const __nv_bfloat16*)d_in[0], (__nv_bfloat16*)d_out);
}
```

```cpp
#include <cuda_runtime.h>
#include <cuda_bf16.h>
#include <cuda.h>
#include <stdint.h>

static constexpr int SEQ = 2048;
static constexpr int NHEAD = 32;
static constexpr int QPC = 512;
static constexpr int NTHREADS = 512;
static constexpr int NMAIN = NHEAD * (SEQ / QPC);
static constexpr int NHELP = 4;
static constexpr int NP = 88;
static constexpr int HB = 3;
static constexpr int SW = 3;
static constexpr int BOX = 256;
static constexpr int HKEYS = HB * 128;
static constexpr uint32_t KV_BYTES = 8u * HKEYS * 32u;
static constexpr uint32_t OFF_K = 0;
static constexpr uint32_t OFF_V = KV_BYTES;
static constexpr uint32_t OFF_ONES = 2 * KV_BYTES;
static constexpr uint32_t OFF_MA = OFF_ONES + 4096;
static constexpr uint32_t OFF_BAR = OFF_MA + 2048;
static constexpr uint32_t OFF_MISC = OFF_BAR + 64;
static constexpr uint32_t SMEM_BYTES = OFF_MISC + 64;
static constexpr uint32_t SMEM_BASE = 1024;

__device__ uint4 g_part[NMAIN * 3 * 128];

template<int N> __device__ __forceinline__ void wg_qk(float* d, const uint32_t* a, uint64_t desc);
template<> __device__ __forceinline__ void wg_qk<40>(float* d, const uint32_t* a, uint64_t desc) {
  asm volatile("wgmma.mma_async.sync.aligned.m64n40k16.f32.bf16.bf16 {%0, %1, %2, %3, %4, %5, %6, %7, %8, %9, %10, %11, %12, %13, %14, %15, %16, %17, %18, %19}, {%20,%21,%22,%23}, %24, 0, 1, 1, 0;\n"
    : "=f"(d[0]), "=f"(d[1]), "=f"(d[2]), "=f"(d[3]), "=f"(d[4]), "=f"(d[5]), "=f"(d[6]), "=f"(d[7]),
      "=f"(d[8]), "=f"(d[9]), "=f"(d[10]), "=f"(d[11]), "=f"(d[12]), "=f"(d[13]), "=f"(d[14]), "=f"(d[15]),
      "=f"(d[16]), "=f"(d[17]), "=f"(d[18]), "=f"(d[19])
    : "r"(a[0]), "r"(a[1]), "r"(a[2]), "r"(a[3]), "l"(desc));
}
template<> __device__ __forceinline__ void wg_qk<64>(float* d, const uint32_t* a, uint64_t desc) {
  asm volatile("wgmma.mma_async.sync.aligned.m64n64k16.f32.bf16.bf16 {%0, %1, %2, %3, %4, %5, %6, %7, %8, %9, %10, %11, %12, %13, %14, %15, %16, %17, %18, %19, %20, %21, %22, %23, %24, %25, %26, %27, %28, %29, %30, %31}, {%32,%33,%34,%35}, %36, 0, 1, 1, 0;\n"
    : "=f"(d[0]), "=f"(d[1]), "=f"(d[2]), "=f"(d[3]), "=f"(d[4]), "=f"(d[5]), "=f"(d[6]), "=f"(d[7]),
      "=f"(d[8]), "=f"(d[9]), "=f"(d[10]), "=f"(d[11]), "=f"(d[12]), "=f"(d[13]), "=f"(d[14]), "=f"(d[15]),
      "=f"(d[16]), "=f"(d[17]), "=f"(d[18]), "=f"(d[19]), "=f"(d[20]), "=f"(d[21]), "=f"(d[22]), "=f"(d[23]),
      "=f"(d[24]), "=f"(d[25]), "=f"(d[26]), "=f"(d[27]), "=f"(d[28]), "=f"(d[29]), "=f"(d[30]), "=f"(d[31])
    : "r"(a[0]), "r"(a[1]), "r"(a[2]), "r"(a[3]), "l"(desc));
}
template<> __device__ __forceinline__ void wg_qk<88>(float* d, const uint32_t* a, uint64_t desc) {
  asm volatile("wgmma.mma_async.sync.aligned.m64n88k16.f32.bf16.bf16 {%0, %1, %2, %3, %4, %5, %6, %7, %8, %9, %10, %11, %12, %13, %14, %15, %16, %17, %18, %19, %20, %21, %22, %23, %24, %25, %26, %27, %28, %29, %30, %31, %32, %33, %34, %35, %36, %37, %38, %39, %40, %41, %42, %43}, {%44,%45,%46,%47}, %48, 0, 1, 1, 0;\n"
    : "=f"(d[0]), "=f"(d[1]), "=f"(d[2]), "=f"(d[3]), "=f"(d[4]), "=f"(d[5]), "=f"(d[6]), "=f"(d[7]),
      "=f"(d[8]), "=f"(d[9]), "=f"(d[10]), "=f"(d[11]), "=f"(d[12]), "=f"(d[13]), "=f"(d[14]), "=f"(d[15]),
      "=f"(d[16]), "=f"(d[17]), "=f"(d[18]), "=f"(d[19]), "=f"(d[20]), "=f"(d[21]), "=f"(d[22]), "=f"(d[23]),
      "=f"(d[24]), "=f"(d[25]), "=f"(d[26]), "=f"(d[27]), "=f"(d[28]), "=f"(d[29]), "=f"(d[30]), "=f"(d[31]),
      "=f"(d[32]), "=f"(d[33]), "=f"(d[34]), "=f"(d[35]), "=f"(d[36]), "=f"(d[37]), "=f"(d[38]), "=f"(d[39]),
      "=f"(d[40]), "=f"(d[41]), "=f"(d[42]), "=f"(d[43])
    : "r"(a[0]), "r"(a[1]), "r"(a[2]), "r"(a[3]), "l"(desc));
}
__device__ __forceinline__ void wg_magic(float* d, uint64_t adesc, uint64_t bdesc) {
  asm volatile("wgmma.mma_async.sync.aligned.m64n88k16.f32.bf16.bf16 {%0, %1, %2, %3, %4, %5, %6, %7, %8, %9, %10, %11, %12, %13, %14, %15, %16, %17, %18, %19, %20, %21, %22, %23, %24, %25, %26, %27, %28, %29, %30, %31, %32, %33, %34, %35, %36, %37, %38, %39, %40, %41, %42, %43}, %44, %45, 1, 1, 1, 0, 0;\n"
    : "+f"(d[0]), "+f"(d[1]), "+f"(d[2]), "+f"(d[3]), "+f"(d[4]), "+f"(d[5]), "+f"(d[6]), "+f"(d[7]),
      "+f"(d[8]), "+f"(d[9]), "+f"(d[10]), "+f"(d[11]), "+f"(d[12]), "+f"(d[13]), "+f"(d[14]), "+f"(d[15]),
      "+f"(d[16]), "+f"(d[17]), "+f"(d[18]), "+f"(d[19]), "+f"(d[20]), "+f"(d[21]), "+f"(d[22]), "+f"(d[23]),
      "+f"(d[24]), "+f"(d[25]), "+f"(d[26]), "+f"(d[27]), "+f"(d[28]), "+f"(d[29]), "+f"(d[30]), "+f"(d[31]),
      "+f"(d[32]), "+f"(d[33]), "+f"(d[34]), "+f"(d[35]), "+f"(d[36]), "+f"(d[37]), "+f"(d[38]), "+f"(d[39]),
      "+f"(d[40]), "+f"(d[41]), "+f"(d[42]), "+f"(d[43])
    : "l"(adesc), "l"(bdesc));
}
__device__ __forceinline__ void wg_pv(float* d, const uint32_t* a, uint64_t desc) {
  asm volatile("wgmma.mma_async.sync.aligned.m64n24k16.f32.bf16.bf16 {%0, %1, %2, %3, %4, %5, %6, %7, %8, %9, %10, %11}, {%12,%13,%14,%15}, %16, 1, 1, 1, 1;\n"
    : "+f"(d[0]), "+f"(d[1]), "+f"(d[2]), "+f"(d[3]), "+f"(d[4]), "+f"(d[5]), "+f"(d[6]), "+f"(d[7]),
      "+f"(d[8]), "+f"(d[9]), "+f"(d[10]), "+f"(d[11])
    : "r"(a[0]), "r"(a[1]), "r"(a[2]), "r"(a[3]), "l"(desc));
}


template<int N> __device__ __forceinline__ void pin(float* r) {
    #pragma unroll
    for (int i = 0; i < N; i++) asm volatile("" : "+f"(r[i]) :: "memory");
}
template<int N> __device__ __forceinline__ void pin(uint32_t* r) {
    #pragma unroll
    for (int i = 0; i < N; i++) asm volatile("" : "+r"(r[i]) :: "memory");
}
__device__ __forceinline__ void wg_fence() { asm volatile("wgmma.fence.sync.aligned;" ::: "memory"); }
__device__ __forceinline__ void wg_commit() { asm volatile("wgmma.commit_group.sync.aligned;" ::: "memory"); }
template<int N> __device__ __forceinline__ void wg_wait() { asm volatile("wgmma.wait_group.sync.aligned %0;" :: "n"(N) : "memory"); }

__device__ __forceinline__ void mbar_init(uint32_t bar, uint32_t count) {
    asm volatile("mbarrier.init.shared::cta.b64 [%0], %1;" :: "r"(bar), "r"(count) : "memory");
}
__device__ __forceinline__ void mbar_expect_tx(uint32_t bar, uint32_t bytes) {
    asm volatile("mbarrier.arrive.expect_tx.shared::cta.b64 _, [%0], %1;" :: "r"(bar), "r"(bytes) : "memory");
}
__device__ __forceinline__ void mbar_arrive(uint32_t bar) {
    asm volatile("mbarrier.arrive.shared::cta.b64 _, [%0];" :: "r"(bar) : "memory");
}
__device__ __forceinline__ void mbar_wait(uint32_t bar, uint32_t parity) {
    asm volatile("{\n.reg .pred p;\n.reg .u32 c;\nmov.u32 c, 0;\n"
                 "WAIT_LOOP:\n"
                 "mbarrier.try_wait.parity.shared::cta.b64 p, [%0], %1;\n"
                 "@p bra WAIT_DONE;\n"
                 "add.u32 c, c, 1;\n"
                 "setp.lt.u32 p, c, 4194304;\n"
                 "@p bra WAIT_LOOP;\n"
                 "WAIT_DONE:\n}\n" :: "r"(bar), "r"(parity) : "memory");
}
__device__ __forceinline__ void tma_load_2d(uint32_t dst, const CUtensorMap* map, int c0, int c1, uint32_t bar) {
    asm volatile("cp.async.bulk.tensor.2d.shared::cluster.global.mbarrier::complete_tx::bytes [%0], [%1, {%3, %4}], [%2];"
                 :: "r"(dst), "l"(map), "r"(bar), "r"(c0), "r"(c1) : "memory");
}
__device__ __forceinline__ float ex2(float x) { float y; asm("ex2.approx.ftz.f32 %0, %1;" : "=f"(y) : "f"(x)); return y; }
__device__ __forceinline__ uint32_t pack_bf16(float lo, float hi) {
    uint32_t r; asm("cvt.rn.bf16x2.f32 %0, %1, %2;" : "=r"(r) : "f"(hi), "f"(lo)); return r;
}
__device__ __forceinline__ uint32_t exp2_pair(float tlo, float thi, uint32_t cbf00) {
    const uint32_t y = __byte_perm(__float_as_uint(tlo), __float_as_uint(thi), 0x6521);
    uint32_t gh; asm("lop3.b32 %0, %1, 0x007F007F, %2, 0xEA;" : "=r"(gh) : "r"(y), "r"(cbf00));
    const uint32_t e = y & 0x7F807F80u;
    uint32_t r; asm("fma.rn.bf16x2 %0, %1, %2, %3;" : "=r"(r) : "r"(gh), "r"(y), "r"(e));
    return r;
}

static constexpr float QSCALE = 0.25f * 1.4426950408889634f;
static constexpr uint64_t DESC_HI = ((uint64_t)((256u >> 4) | (3u << 30))) << 32;
static constexpr uint64_t DESC_HI0 = ((uint64_t)(3u << 30)) << 32;
static constexpr int64_t VSTEP = 32 - (32 << 16);
static constexpr uint64_t VD0 = DESC_HI | (((SMEM_BASE + OFF_V) >> 4) | (((OFF_ONES - OFF_V) >> 4) << 16));
static constexpr int64_t K_FROM_V = -(int64_t)((OFF_V - OFF_K) >> 4);
__device__ __forceinline__ uint64_t dadd(uint64_t d, int64_t x) { return d + (uint64_t)x; }

__device__ __forceinline__ void store_out(__nv_bfloat16* out, int row0, int lane, const float* o, float r0, float r1) {
    uint32_t* p0 = reinterpret_cast<uint32_t*>(out + (size_t)(row0 + (lane >> 2)) * 16) + (lane & 3);
    p0[0] = pack_bf16(o[0] * r0, o[1] * r0);
    p0[4] = pack_bf16(o[4] * r0, o[5] * r0);
    p0[64] = pack_bf16(o[2] * r1, o[3] * r1);
    p0[68] = pack_bf16(o[6] * r1, o[7] * r1);
}

__device__ __forceinline__ void safe_block(const __nv_bfloat16* __restrict__ q, __nv_bfloat16* __restrict__ out, int row0, int lane) {
    const uint32_t* q0 = reinterpret_cast<const uint32_t*>(q + (size_t)(row0 + (lane >> 2)) * 16) + (lane & 3);
    uint32_t qa[4] = {q0[0], q0[64], q0[4], q0[68]};
    float o[12];
    #pragma unroll
    for (int i = 0; i < 12; i++) o[i] = 0.f;
    float m0 = -INFINITY, m1 = -INFINITY;
    #pragma unroll 1
    for (int j = 0; j < SEQ / 64; j++) {
        float s[32];
        uint32_t p[16];
        wg_fence();
        wg_qk<64>(s, qa, dadd(VD0, K_FROM_V + j * 128));
        wg_commit();
        wg_wait<0>();
        pin<32>(s);
        float x0 = m0, x1 = m1;
        #pragma unroll
        for (int i = 0; i < 8; i++) {
            x0 = fmaxf(x0, fmaxf(s[4 * i], s[4 * i + 1]));
            x1 = fmaxf(x1, fmaxf(s[4 * i + 2], s[4 * i + 3]));
        }
        x0 = fmaxf(x0, __shfl_xor_sync(0xffffffffu, x0, 1));
        x0 = fmaxf(x0, __shfl_xor_sync(0xffffffffu, x0, 2));
        x1 = fmaxf(x1, __shfl_xor_sync(0xffffffffu, x1, 1));
        x1 = fmaxf(x1, __shfl_xor_sync(0xffffffffu, x1, 2));
        const float a0 = exp2f((m0 - x0) * QSCALE), a1 = exp2f((m1 - x1) * QSCALE);
        m0 = x0; m1 = x1;
        #pragma unroll
        for (int i = 0; i < 3; i++) { o[4 * i] *= a0; o[4 * i + 1] *= a0; o[4 * i + 2] *= a1; o[4 * i + 3] *= a1; }
        #pragma unroll
        for (int i = 0; i < 8; i++) {
            p[2 * i] = pack_bf16(exp2f((s[4 * i] - m0) * QSCALE), exp2f((s[4 * i + 1] - m0) * QSCALE));
            p[2 * i + 1] = pack_bf16(exp2f((s[4 * i + 2] - m1) * QSCALE), exp2f((s[4 * i + 3] - m1) * QSCALE));
        }
        wg_fence();
        #pragma unroll
        for (int k = 0; k < 4; k++) wg_pv(o, p + 4 * k, dadd(VD0, (j * 4 + k) * VSTEP));
        wg_commit();
        wg_wait<0>();
        pin<12>(o);
    }
    store_out(out, row0, lane, o, 1.0f / o[8], 1.0f / o[10]);
}

__device__ __forceinline__ void scale_q(const uint32_t* raw, uint32_t* qa, uint32_t& qm) {
    #pragma unroll
    for (int i = 0; i < 4; i++) {
        uint32_t t;
        asm("mul.rn.bf16x2 %0, %1, %2;" : "=r"(t) : "r"(raw[i]), "r"(0xBA2CBA2Cu));
        asm("fma.rn.bf16x2 %0, %1, %2, %3;" : "=r"(qa[i]) : "r"(raw[i]), "r"(0x3EB93EB9u), "r"(t));
    }
    #pragma unroll
    for (int i = 0; i < 2; i++) {
        uint32_t a;
        asm("mul.rn.bf16x2 %0, %1, %1;" : "=r"(a) : "r"(qa[i]));
        asm("fma.rn.bf16x2 %0, %1, %1, %0;" : "+r"(a) : "r"(qa[i + 2]));
        qm = __vmaxu2(qm, a);
    }
}

__device__ __forceinline__ void tiles(int n, float* s, float* o, const uint32_t* qa, uint32_t& vlo,
                                      uint64_t md, uint64_t od, uint32_t cbf00) {
    const uint32_t vend = vlo + n * (uint32_t)(8 * VSTEP);
    #pragma unroll 1
    do {
        uint64_t vd;
        asm("mov.b64 %0, {%1, %2};" : "=l"(vd) : "r"(vlo), "r"((uint32_t)(od >> 32)));
        #pragma unroll
        for (int h = 0; h < 2; h++) {
            const int ks[4] = {h == 0 ? 0 : 3, h == 0 ? 1 : 4, h == 0 ? 2 : 5, h == 0 ? 7 : 6};
            uint32_t p[16];
            if (h == 0) { wg_wait<0>(); pin<64>(s); }
            #pragma unroll
            for (int j = 0; j < 4; j++) {
                #pragma unroll
                for (int r = 0; r < 4; r++) {
                    const int i = ks[j] * 4 + r;
                    if (i < NP / 4) p[4 * j + r] = exp2_pair(s[2 * i], s[2 * i + 1], cbf00);
                    else p[4 * j + r] = pack_bf16(ex2(s[2 * i]), ex2(s[2 * i + 1]));
                }
            }
            pin<16>(p);
            wg_fence();
            wg_pv(o, p, dadd(vd, ks[0] * VSTEP));
            if (h == 1) wg_qk<128 - NP>(s + NP / 2, qa, dadd(vd, K_FROM_V + 256 + NP * 2));
            wg_pv(o, p + 4, dadd(vd, ks[1] * VSTEP));
            if (h == 1) {
                wg_commit(); wg_wait<1>(); wg_fence();
                wg_qk<NP>(s, qa, dadd(vd, K_FROM_V + 256));
            }
            wg_pv(o, p + 8, dadd(vd, ks[2] * VSTEP));
            if (h == 1) wg_magic(s, md, od);
            wg_pv(o, p + 12, dadd(vd, ks[3] * VSTEP));
            wg_commit();
        }
        vlo += (uint32_t)(8 * VSTEP);
    } while (vlo != vend);
}

__global__ void __launch_bounds__(NTHREADS, 1)
attn_kernel(const __grid_constant__ CUtensorMap tmK, const __grid_constant__ CUtensorMap tmV,
            const __grid_constant__ CUtensorMap tmKh, const __grid_constant__ CUtensorMap tmVh,
            const __nv_bfloat16* __restrict__ q, const __nv_bfloat16* __restrict__ kg, const __nv_bfloat16* __restrict__ vg,
            __nv_bfloat16* __restrict__ out, const uint64_t md, const uint64_t od) {
    extern __shared__ __align__(1024) uint8_t sptr[];
    const uint32_t sbase = (uint32_t)__cvta_generic_to_shared(sptr);
    const int tid = threadIdx.x, lane = tid & 31;
    const int warp = __shfl_sync(0xffffffffu, tid >> 5, 0), wg = warp >> 2;
    const uint32_t bar0 = sbase + OFF_BAR;
    const uint32_t cbf00 = 0xBF00BF00u ^ (uint32_t)(gridDim.y - 1);
    if ((sbase & 0x3FFFFu) != SMEM_BASE) __trap();

    const bool is_main = blockIdx.x >= NHELP;
    const int cta = blockIdx.x - NHELP;
    const int head = is_main ? (cta >> 2) : blockIdx.x * 8;
    const int row0 = is_main ? cta * QPC + warp * 16 : head * SEQ + wg * QPC + 256 + SW * 64 + (warp & 3) * 16;
    const int qstep = is_main ? 256 * 8 : SEQ * 8;
    const uint4 k0 = __ldg(reinterpret_cast<const uint4*>(kg + (size_t)head * SEQ * 16) + tid);
    const uint32_t* qp = reinterpret_cast<const uint32_t*>(q + (size_t)(row0 + (lane >> 2)) * 16) + (lane & 3);
    uint32_t raw[4] = {__ldg(qp), __ldg(qp + 64), __ldg(qp + 4), __ldg(qp + 68)};
    const uint4 v0 = __ldg(reinterpret_cast<const uint4*>(vg + (size_t)head * SEQ * 16) + tid);
    uint32_t* misc = reinterpret_cast<uint32_t*>(sptr + OFF_MISC);
    auto fetch_box = [&](int b) {
        const uint32_t bytes = is_main ? BOX * 32 : HKEYS * 32;
        const int row = is_main ? (head * SEQ + b * BOX) / 4 : ((head + b + 1) * SEQ - HKEYS) / 4;
        const uint32_t bar = bar0 + 8 * ((is_main && b > 3) ? 3 : b);
        mbar_expect_tx(bar, 2 * bytes);
        tma_load_2d(sbase + OFF_K + b * bytes, is_main ? &tmK : &tmKh, 0, row, bar);
        tma_load_2d(sbase + OFF_V + b * bytes, is_main ? &tmV : &tmVh, 0, row, bar);
    };
    if (lane == 0 && warp < 4) {
        mbar_init(bar0 + 8 * warp, !is_main ? 1 : (warp == 0 ? NTHREADS / 32 : (warp == 3 ? 5 : 1)));
        mbar_init(bar0 + 8 * (warp + 4), 1);
        asm volatile("fence.mbarrier_init.release.cluster;" ::: "memory");
        if (warp == 1 || (warp == 0 && !is_main)) fetch_box(warp);
    }
    __syncwarp();
    reinterpret_cast<uint2*>(sptr + OFF_ONES)[tid] = make_uint2(0x3F803F80u, 0x3F803F80u);
    if (tid < 64) reinterpret_cast<uint32_t*>(sptr + OFF_MA)[tid] = ((tid & 7) == 0) ? 0x3ED643BFu : (((tid & 7) == 1) ? 0x0000B9A8u : 0u);
    else if (tid == 64) misc[0] = 0u;
    if (is_main) {
        const uint32_t off = (tid ^ ((tid >> 3) & 7)) << 4;
        *reinterpret_cast<uint4*>(sptr + OFF_K + off) = k0;
        *reinterpret_cast<uint4*>(sptr + OFF_V + off) = v0;
    }
    asm volatile("fence.proxy.async.shared::cta;" ::: "memory");
    uint32_t qm = 0u;
    bool bad = false;
    int seg = is_main ? 0 : 4;
    const int nlast = is_main ? (wg == SW ? 16 - HB : 16) : HB;
    const int npass = is_main ? 2 : 8;
    uint32_t vlo = (uint32_t)VD0;
    #pragma unroll 1
    for (int pass = 0; pass < npass; pass++) {
        uint32_t qa[4];
        scale_q(raw, qa, qm);
        float s[64], o[12];
        #pragma unroll
        for (int i = 0; i < 12; i++) o[i] = 0.f;
        pin<12>(o);
        if (pass == 0) __syncthreads();
        if (is_main) vlo = (uint32_t)VD0; else mbar_wait(bar0 + 8 * pass, 0);
        wg_fence();
        wg_qk<NP>(s, qa, dadd(DESC_HI | vlo, K_FROM_V));
        wg_qk<128 - NP>(s + NP / 2, qa, dadd(DESC_HI | vlo, K_FROM_V + NP * 2));
        wg_magic(s, md, od);
        wg_commit();
        if (pass == 0) {
            if (lane == 0 && warp < 4) {
                if (warp >= 2) fetch_box(warp);
                fetch_box(warp + 4);
            }
            __syncwarp();
        }
        qp += qstep;
        if (pass + 1 < npass) {
            asm volatile("prefetch.global.L2 [%0];" :: "l"(qp));
            asm volatile("prefetch.global.L2 [%0];" :: "l"(qp + 64));
        }
        #pragma unroll 1
        do {
            if (seg >= 1 && seg <= 3) mbar_wait(bar0 + 8 * seg, 0);
            const int n = (seg >= 4) ? nlast : ((0xB221 >> (4 * seg)) & 15);
            tiles(n, s, o, qa, vlo, md, od, cbf00);
        } while (++seg < 4);
        if (pass + 1 < npass) { raw[0] = __ldg(qp); raw[1] = __ldg(qp + 64); raw[2] = __ldg(qp + 4); raw[3] = __ldg(qp + 68); }
        wg_wait<0>();
        pin<12>(o);
        if (!is_main) {
            uint32_t w[10];
            #pragma unroll
            for (int i = 0; i < 10; i++) { w[i] = __float_as_uint(o[i < 9 ? i : 10]); if (w[i] == 0u) w[i] = 0x80000000u; }
            uint4* dst = g_part + ((head + pass) * 4 + wg) * 384 + (tid & 127);
            __stcg(dst, make_uint4(w[0], w[1], w[2], w[3]));
            __stcg(dst + 128, make_uint4(w[4], w[5], w[6], w[7]));
            __stcg(dst + 256, make_uint4(w[8], w[9], 0u, 0u));
            continue;
        }
        if (pass == 1 && wg == SW) {
            uint4* src = g_part + cta * 384 + (tid & 127);
            uint32_t w[10];
            asm volatile("{\n.reg .pred p;\n.reg .u32 c, m, z0, z1;\nmov.u32 c, 0;\n"
                         "PART_LOOP:\n"
                         "ld.relaxed.gpu.global.v4.u32 {%0, %1, %2, %3}, [%10];\n"
                         "ld.relaxed.gpu.global.v4.u32 {%4, %5, %6, %7}, [%10 + 2048];\n"
                         "ld.relaxed.gpu.global.v4.u32 {%8, %9, z0, z1}, [%10 + 4096];\n"
                         "min.u32 m, %0, %1;\nmin.u32 m, m, %2;\nmin.u32 m, m, %3;\nmin.u32 m, m, %4;\nmin.u32 m, m, %5;\n"
                         "min.u32 m, m, %6;\nmin.u32 m, m, %7;\nmin.u32 m, m, %8;\nmin.u32 m, m, %9;\n"
                         "setp.ne.u32 p, m, 0;\n"
                         "vote.sync.all.pred p, p, 0xffffffff;\n"
                         "@p bra.uni PART_DONE;\n"
                         "add.u32 c, c, 1;\n"
                         "setp.lt.u32 p, c, 4194304;\n"
                         "@p bra.uni PART_LOOP;\n"
                         "PART_DONE:\n}\n"
                         : "=r"(w[0]), "=r"(w[1]), "=r"(w[2]), "=r"(w[3]), "=r"(w[4]), "=r"(w[5]), "=r"(w[6]), "=r"(w[7]), "=r"(w[8]), "=r"(w[9])
                         : "l"(src) : "memory");
            const uint4 z = make_uint4(0u, 0u, 0u, 0u);
            __stcg(src, z); __stcg(src + 128, z); __stcg(src + 256, z);
            #pragma unroll
            for (int i = 0; i < 10; i++) o[i < 9 ? i : 10] += __uint_as_float(w[i]);
        }
        {
            const float amax0 = fmaxf(fmaxf(fabsf(o[0]), fabsf(o[1])), fmaxf(fabsf(o[4]), fabsf(o[5])));
            const float amax1 = fmaxf(fmaxf(fabsf(o[2]), fabsf(o[3])), fmaxf(fabsf(o[6]), fabsf(o[7])));
            const float sum = ((o[0] + o[1]) + (o[2] + o[3])) + ((o[4] + o[5]) + (o[6] + o[7]));
            if (!(fabsf(sum) < 1e37f) || !(fminf(amax0, amax1) > 1e-25f)) bad = true;
        }
        float r0, r1;
        asm("rcp.approx.ftz.f32 %0, %1;" : "=f"(r0) : "f"(o[8]));
        asm("rcp.approx.ftz.f32 %0, %1;" : "=f"(r1) : "f"(o[10]));
        store_out(out, row0 + pass * 256, lane, o, r0, r1);
        if (pass == 0) {
            uint32_t m2 = 0u;
            const uint4* kp = reinterpret_cast<const uint4*>(sptr + OFF_K) + tid;
            #pragma unroll
            for (int i = 0; i < 8; i++) {
                const uint4 w = kp[i * NTHREADS];
                uint32_t a;
                asm("mul.rn.bf16x2 %0, %1, %1;" : "=r"(a) : "r"(w.x));
                asm("fma.rn.bf16x2 %0, %1, %1, %0;" : "+r"(a) : "r"(w.y));
                asm("fma.rn.bf16x2 %0, %1, %1, %0;" : "+r"(a) : "r"(w.z));
                asm("fma.rn.bf16x2 %0, %1, %1, %0;" : "+r"(a) : "r"(w.w));
                m2 = __vmaxu2(m2, a);
            }
            const float sN = __uint_as_float(m2 << 16) + __uint_as_float(m2 & 0xffff0000u);
            const uint32_t km = __reduce_max_sync(0xffffffffu, __float_as_uint(sN) & 0x7fffffffu);
            if (lane == 0) { atomicMax(misc, km); mbar_arrive(bar0); }
        }
    }
    if (!is_main) return;
    mbar_wait(bar0, 0);
    {
        const float kn2 = 2.f * __uint_as_float(*reinterpret_cast<volatile uint32_t*>(misc));
        float qn2 = __uint_as_float(qm << 16) + __uint_as_float(qm & 0xffff0000u);
        qn2 += __shfl_xor_sync(0xffffffffu, qn2, 1);
        qn2 += __shfl_xor_sync(0xffffffffu, qn2, 2);
        if (!(qn2 * kn2 * 1.1f <= 40.f * 40.f)) bad = true;
    }
    uint32_t anybad;
    asm volatile("{\n.reg .pred p, q;\nsetp.ne.u32 q, %1, 0;\nbarrier.cta.red.or.aligned.pred p, %2, 128, q;\nselp.u32 %0, 1, 0, p;\n}\n"
                 : "=r"(anybad) : "r"((uint32_t)bad), "r"(wg + 1) : "memory");
    if (anybad) {
        #pragma unroll 1
        for (int pass = 0; pass < 2; pass++) safe_block(q, out, row0 + pass * 256, lane);
    }
}

typedef CUresult (*PFN_encodeTiled)(CUtensorMap*, CUtensorMapDataType, cuuint32_t, void*, const cuuint64_t*, const cuuint64_t*,
                                    const cuuint32_t*, const cuuint32_t*, CUtensorMapInterleave, CUtensorMapSwizzle,
                                    CUtensorMapL2promotion, CUtensorMapFloatOOBfill);

extern "C" void kernel_launch(void* const* d_in, const int* in_sizes, int n_in, void* d_out, int out_size) {
    static PFN_encodeTiled encode = nullptr;
    if (!encode) {
        cudaDriverEntryPointQueryResult qres;
        void* fn = nullptr;
        cudaGetDriverEntryPoint("cuTensorMapEncodeTiled", &fn, cudaEnableDefault, &qres);
        encode = (PFN_encodeTiled)fn;
        cudaFuncSetAttribute(attn_kernel, cudaFuncAttributeMaxDynamicSharedMemorySize, SMEM_BYTES);
    }
    CUtensorMap tm[4];
    cuuint64_t gdim[2] = {64, (cuuint64_t)NHEAD * SEQ / 4};
    cuuint64_t gstr[1] = {128};
    cuuint32_t estr[2] = {1, 1};
    for (int i = 0; i < 4; i++) {
        cuuint32_t box[2] = {64, (cuuint32_t)(i < 2 ? BOX : HKEYS) / 4};
        encode(&tm[i], CU_TENSOR_MAP_DATA_TYPE_BFLOAT16, 2, d_in[1 + (i & 1)], gdim, gstr, box, estr, CU_TENSOR_MAP_INTERLEAVE_NONE,
               CU_TENSOR_MAP_SWIZZLE_128B, CU_TENSOR_MAP_L2_PROMOTION_L2_256B, CU_TENSOR_MAP_FLOAT_OOB_FILL_NONE);
    }
    const uint64_t md = DESC_HI0 | (((SMEM_BASE + OFF_MA) >> 4) | (1u << 16));
    const uint64_t od = DESC_HI | (((SMEM_BASE + OFF_ONES) >> 4) | (1u << 16));
    attn_kernel<<<NMAIN + NHELP, NTHREADS, SMEM_BYTES>>>(tm[0], tm[1], tm[2], tm[3], (const __nv_bfloat16*)d_in[0],
                                                         (const __nv_bfloat16*)d_in[1], (const __nv_bfloat16*)d_in[2],
                                                         (__nv_bfloat16*)d_out, md, od);
}
```
